```python
import torch

def _softmax(x, axis=-1):
    return torch.softmax(x, dim=axis)
def _gelu(x):
    return torch.nn.functional.gelu(x, approximate="tanh")
def _silu(x):
    return torch.nn.functional.silu(x)
def _sigmoid(x):
    return torch.sigmoid(x)
def _layernorm(x, axis=-1, eps=1e-5):
    m = x.mean(dim=axis, keepdim=True)
    v = x.var(dim=axis, keepdim=True, unbiased=False)
    return (x - m) / torch.sqrt(v + eps)
def _scatter_add(tgt, idx, src, axis=0):
    return tgt.clone().index_add_(axis, idx, src)
def _segment_sum(src, seg, n):
    out = torch.zeros((n,) + src.shape[1:], dtype=src.dtype)
    return out.index_add_(0, seg, src)
def _pad(x, pw):
    flat = tuple(v for pair in reversed(pw) for v in pair)
    return torch.nn.functional.pad(x, flat)

kernel_name = 'gated_mix__sliding_block__dense_activation_relu__prompt'

def setup_inputs():

    _w = (lambda a: (lambda t: t.to(torch.bfloat16) if t.is_floating_point() else t)(torch.as_tensor(a)))
    def _A_setup():
        B, S, D = 1, 2048, 512
        return {
            "x": _w((lambda *s: torch.randn(*s, dtype=torch.bfloat16) * 0.05)(B, S, D)),
            "wqkv": _w((lambda *s: torch.randn(*s, dtype=torch.bfloat16) * 0.8)(D, 3 * D)),
            "wo": _w((lambda *s: torch.randn(*s, dtype=torch.bfloat16) * 0.05)(D, D)),
        }
    _A_in = _A_setup()

    def _B_setup():
        B, S, D, Dff = 1, 2048, 512, 1376
        return {
            "x": _w((lambda *s: torch.randn(*s, dtype=torch.bfloat16) * 0.05)(B, S, D)),
            "w1": _w((lambda *s: torch.randn(*s, dtype=torch.bfloat16) * 0.05)(D, Dff)),
            "w2": _w((lambda *s: torch.randn(*s, dtype=torch.bfloat16) * 0.05)(Dff, D)),
        }
    _B_in = _B_setup()

    return {
        "A_x": _A_in["x"],
        "A_wqkv": _A_in["wqkv"],
        "A_wo": _A_in["wo"],
        "B_x": _B_in["x"],
        "B_w1": _B_in["w1"],
        "B_w2": _B_in["w2"],
        "gate_w": _w((lambda *s: torch.randn(*s, dtype=torch.bfloat16) * 0.05)(512) * 16.0),
    }

def reference(A_x, A_wqkv, A_wo, B_x, B_w1, B_w2, gate_w):
    def _A_ref(x, wqkv, wo):
        B, S, D = x.shape
        H = 32; Dh = D // H; W = 256
        qkv = (lambda x, *d: x.permute(*d))((x @ wqkv).reshape(B, S, 3, H, Dh), 2, 0, 3, 1, 4)
        q, k, v = qkv[0], qkv[1], qkv[2]
        scores = torch.einsum("bhqd,bhkd->bhqk", q, k) * (Dh ** -0.5)
        idx = torch.arange(S)
        mask = (idx[:, None] - idx[None, :] >= 0) & (idx[:, None] - idx[None, :] < W)
        scores = torch.where(mask[None, None], scores, -1e9)
        p = _softmax(scores, axis=-1)
        o = torch.einsum("bhqk,bhkd->bhqd", p, v)
        return (lambda x, *d: x.permute(*d))(o, 0, 2, 1, 3).reshape(B, S, D) @ wo

    def _B_ref(x, w1, w2):
        h = torch.einsum("bsd,df->bsf", x, w1)
        zero = torch.zeros_like(h)
        h = torch.maximum(h, zero)
        return torch.einsum("bsf,fd->bsd", h, w2)

    x = A_x
    g = _sigmoid((x * gate_w).sum(-1, keepdims=True))
    a = _A_ref(x, A_wqkv, A_wo)
    b = _B_ref(x, B_w1, B_w2)
    return g * a + (1 - g) * b
```

```cpp
#include <cuda_runtime.h>
#include <cuda_bf16.h>
#include <cuda.h>
#include <stdint.h>

namespace {

constexpr uint32_t G_FLAGS = 0;
constexpr uint32_t G_GATE = 4096;
constexpr uint32_t G_KV = 32768;
constexpr uint32_t G_O = G_KV + 512 * 8192;
constexpr uint32_t G_H = G_O + 16 * 4 * 32768;
constexpr uint32_t G_END = G_H + 16 * 172 * 2048;
__device__ __align__(1024) unsigned char g_scratch[G_END];
#define g_kv (scr + G_KV)
#define g_o (scr + G_O)
#define g_h (scr + G_H)
#define g_flags ((unsigned int*)(scr + G_FLAGS))
#define g_gate ((unsigned long long*)(scr + G_GATE))
#define TR(id) do {} while (0)
#define TRV(id, v) do {} while (0)
#define TRG(id) do {} while (0)
#define TRC(id) do {} while (0)
#define TRP(id) do {} while (0)
#define TR3(id) do {} while (0)
#define TR_END() do {} while (0)
#define TR_EXTRA 0

__device__ __forceinline__ int HEAD(int j, int s) { return (j >> 1) * 8 + (j & 1) * 2 + (s & 1) + (s >> 1) * 4; }
__device__ __forceinline__ int F_KV(int i, int j) { return i * 32 + (j >> 1) * 8 + (j & 1); }
__device__ __forceinline__ int F_O(int i, int s) { return i * 32 + s * 8 + 4; }
__device__ __forceinline__ int F_H(int i, int pass, int kh) { return i * 32 + ((pass * 2 + kh) & 3) * 8 + 5 + (pass >> 1); }

constexpr uint32_t SM_X = 0;
constexpr uint32_t SM_R = 131072;
constexpr uint32_t SM_K = SM_R;
constexpr uint32_t SM_V = SM_R + 12288;
constexpr uint32_t SM_W = SM_R + 32768;
constexpr uint32_t SM_Q = SM_R + 81920;
constexpr uint32_t SM_GW = 229376;
constexpr uint32_t SM_G = SM_GW + 1024;
constexpr uint32_t SM_BAR = SM_G + 1024;
constexpr uint32_t SM_EP = SM_BAR + 576;
constexpr uint32_t SM_TOTAL = SM_BAR + 580 + TR_EXTRA;
enum { B_QF = 0, B_QE = 8, B_WF = 16, B_WE = 22, B_GF = 28, B_GE = 32, B_KF = 36, B_KE = 40, B_EP = 44, B_SKV = 45, B_SKB = 46, B_SH = 47,
       B_SO = 50, B_DONE = 54, B_GO = 55, B_G = 56, B_Q = 57, B_WO = 58, B_QD = 60, B_PF = 61, B_PE = 65, B_FL = 66, B_N = 72 };

#define ATT_START 12
#define H_LAST 3
#define WO_AT 7
#define PF_PACE 360
#define PF2_AT 2
#define ONEBR 1
#define POSTB 0
#define SEND1 5
#define SELFREL 0
#define QB 2
#define BF 2
#define K_EARLY 0
#define H_FIRST 1
#define O3N 4
#define KVB 0
#define Z_PACE 400
#define Z_AT B_QD
#define K_N 4
#define Q0_AFTER 1
#define Q2_AFTER 1
#define Q3_AFTER 3
#define Q1_AFTER 4
#define K_CUM(v) ((v) >= K_N ? 16 : (v) * ((15 + K_N) / K_N))
#define GMODE 0
#define H_CUM(v) ((v) >= H_LAST ? 8 : (v) * ((7 + H_LAST) / H_LAST))
template <int V> struct IC { static constexpr int value = V; };
constexpr int SPIN_LIMIT = 1 << 22;

__device__ __forceinline__ void mbar_init(uint32_t bar, uint32_t cnt) { asm volatile("mbarrier.init.shared::cta.b64 [%0], %1;" :: "r"(bar), "r"(cnt)); }
__device__ __forceinline__ void mbar_expect_tx(uint32_t bar, uint32_t bytes) { asm volatile("mbarrier.arrive.expect_tx.shared::cta.b64 _, [%0], %1;" :: "r"(bar), "r"(bytes) : "memory"); }
__device__ __forceinline__ void mbar_arrive_if(uint32_t bar, bool p) {
  asm volatile("{\n.reg .pred p;\nsetp.ne.b32 p, %1, 0;\n@p mbarrier.arrive.shared::cta.b64 _, [%0];\n}" :: "r"(bar), "r"((int)p) : "memory");
}
__device__ __forceinline__ bool mbar_try(uint32_t bar, uint32_t parity) {
  uint32_t ok;
  asm volatile("{\n.reg .pred p;\nmbarrier.try_wait.parity.shared::cta.b64 p, [%1], %2;\nselp.b32 %0, 1, 0, p;\n}" : "=r"(ok) : "r"(bar), "r"(parity) : "memory");
  return ok;
}
__device__ __forceinline__ bool mbar_test(uint32_t bar, uint32_t parity) {
  uint32_t ok;
  asm volatile("{\n.reg .pred p;\nmbarrier.test_wait.parity.shared::cta.b64 p, [%1], %2;\nselp.b32 %0, 1, 0, p;\n}" : "=r"(ok) : "r"(bar), "r"(parity) : "memory");
  return ok;
}
__device__ __forceinline__ void wg_fence() { asm volatile("wgmma.fence.sync.aligned;" ::: "memory"); }
__device__ __forceinline__ void wg_commit() { asm volatile("wgmma.commit_group.sync.aligned;" ::: "memory"); }
template <int N> __device__ __forceinline__ void wg_wait() { asm volatile("wgmma.wait_group.sync.aligned %0;" :: "n"(N) : "memory"); }
__device__ __forceinline__ void mbar_wait(uint32_t bar, uint32_t parity) {
  asm volatile("{\n.reg .pred p;\nW%=:\nmbarrier.try_wait.parity.shared::cta.b64 p, [%0], %1;\n@!p bra W%=;\n}" :: "r"(bar), "r"(parity) : "memory");
}
__device__ __forceinline__ void mbar_spin(uint32_t bar, uint32_t parity) {
  asm volatile("{\n.reg .pred p;\nW%=:\nmbarrier.try_wait.parity.shared::cta.b64 p, [%0], %1;\n@!p pmevent 0;\n@!p bra W%=;\n}" :: "r"(bar), "r"(parity) : "memory");
}
__device__ __forceinline__ void mbar_wait_bounded(uint32_t bar, uint32_t parity) {
  int it = 0;
  while (!mbar_try(bar, parity)) {
    if (++it > SPIN_LIMIT) __trap();
  }
}
__device__ __forceinline__ bool elect_one() {
  uint32_t p; asm volatile("{\n.reg .pred P;\nelect.sync _|P, 0xffffffff;\nselp.b32 %0, 1, 0, P;\n}" : "=r"(p)); return p;
}
__device__ __forceinline__ void bulk_g2s(uint32_t dst, const void* src, uint32_t bytes, uint32_t bar) {
  asm volatile("cp.async.bulk.shared::cluster.global.mbarrier::complete_tx::bytes [%0], [%1], %2, [%3];" :: "r"(dst), "l"(src), "r"(bytes), "r"(bar) : "memory");
}
__device__ __forceinline__ void tma_2d(uint32_t dst, const CUtensorMap* tm, int c0, int c1, uint32_t bar) {
  asm volatile("cp.async.bulk.tensor.2d.shared::cluster.global.mbarrier::complete_tx::bytes [%0], [%1, {%3, %4}], [%2];" :: "r"(dst), "l"(tm), "r"(bar), "r"(c0), "r"(c1) : "memory");
}
__device__ __forceinline__ void tma_3d(uint32_t dst, const CUtensorMap* tm, int c0, int c1, int c2, uint32_t bar) {
  asm volatile("cp.async.bulk.tensor.3d.shared::cluster.global.mbarrier::complete_tx::bytes [%0], [%1, {%3, %4, %5}], [%2];" :: "r"(dst), "l"(tm), "r"(bar), "r"(c0), "r"(c1), "r"(c2) : "memory");
}
__device__ __forceinline__ void tma_4d(uint32_t dst, const CUtensorMap* tm, int c0, int c1, int c2, int c3, uint32_t bar) {
  asm volatile("cp.async.bulk.tensor.4d.shared::cluster.global.mbarrier::complete_tx::bytes [%0], [%1, {%3, %4, %5, %6}], [%2];" :: "r"(dst), "l"(tm), "r"(bar), "r"(c0), "r"(c1), "r"(c2), "r"(c3) : "memory");
}
__device__ __forceinline__ void l2_prefetch(const void* p, uint32_t bytes) { asm volatile("cp.async.bulk.prefetch.L2.global [%0], %1;" :: "l"(p), "r"(bytes) : "memory"); }
__device__ __forceinline__ void tma_prefetch_2d(const CUtensorMap* tm, int c0, int c1) {
  asm volatile("cp.async.bulk.prefetch.tensor.2d.L2.global [%0, {%1, %2}];" :: "l"(tm), "r"(c0), "r"(c1) : "memory");
}
__device__ __forceinline__ void fence_async() { asm volatile("fence.proxy.async.global;" ::: "memory"); }
__device__ __forceinline__ void fence_async_smem() { asm volatile("fence.proxy.async.shared::cta;" ::: "memory"); }
__device__ __forceinline__ uint32_t ld_acquire(const unsigned int* p) { uint32_t v; asm volatile("ld.acquire.gpu.global.u32 %0, [%1];" : "=r"(v) : "l"(p) : "memory"); return v; }
__device__ __forceinline__ uint32_t ld_relaxed(const unsigned int* p) { uint32_t v; asm volatile("ld.relaxed.gpu.global.u32 %0, [%1];" : "=r"(v) : "l"(p) : "memory"); return v; }
__device__ __forceinline__ void flag_release(unsigned int* p) {
  asm volatile("{\n.reg .pred p;\nelect.sync _|p, 0xffffffff;\n@p red.release.gpu.global.add.u32 [%0], 1;\n}" :: "l"(p) : "memory");
}
__device__ __forceinline__ void acquire_for_tma() { asm volatile("fence.acquire.gpu;\nfence.proxy.async.global;" ::: "memory"); }
__device__ __forceinline__ void flag_wait(const unsigned int* p, uint32_t target) {
  while (!__all_sync(0xffffffffu, (int)(ld_relaxed(p) - target) >= 0)) {}
  acquire_for_tma();
}
__device__ __forceinline__ void stsm4(uint32_t a, uint32_t v0, uint32_t v1, uint32_t v2, uint32_t v3) {
  asm volatile("stmatrix.sync.aligned.m8n8.x4.shared.b16 [%0], {%1, %2, %3, %4};" :: "r"(a), "r"(v0), "r"(v1), "r"(v2), "r"(v3) : "memory");
}
__device__ __forceinline__ uint32_t clock32() { uint32_t c; asm volatile("mov.u32 %0, %%clock;" : "=r"(c)); return c; }
__device__ __forceinline__ uint64_t mkd(uint32_t lo, uint32_t hi) { uint64_t d; asm("mov.b64 %0, {%1, %2};" : "=l"(d) : "r"(lo), "r"(hi)); return d; }
constexpr uint32_t HI_SW128 = 64u | (1u << 30);
__device__ __forceinline__ float ex2(float x) { float y; asm volatile("ex2.approx.ftz.f32 %0, %1;" : "=f"(y) : "f"(x)); return y; }
__device__ __forceinline__ uint32_t pack2(float lo, float hi) { uint32_t r; asm volatile("cvt.rn.bf16x2.f32 %0, %1, %2;" : "=r"(r) : "f"(hi), "f"(lo)); return r; }
__device__ __forceinline__ uint32_t pack2_relu(float lo, float hi) { uint32_t r; asm volatile("cvt.rn.relu.bf16x2.f32 %0, %1, %2;" : "=r"(r) : "f"(hi), "f"(lo)); return r; }
__device__ __forceinline__ float bf_lo(uint32_t v) { return __uint_as_float(v << 16); }
__device__ __forceinline__ float bf_hi(uint32_t v) { return __uint_as_float(v & 0xFFFF0000u); }
__device__ __forceinline__ float bf_round(float x) { return __bfloat162float(__float2bfloat16_rn(x)); }
__device__ __forceinline__ void stg32(void* p, uint32_t v) { asm volatile("st.global.b32 [%0], %1;" :: "l"(p), "r"(v) : "memory"); }
__device__ __forceinline__ void sts32(uint32_t a, uint32_t v) { asm volatile("st.shared.b32 [%0], %1;" :: "r"(a), "r"(v) : "memory"); }
__device__ __forceinline__ uint4 lds128(uint32_t a) { uint4 v; asm volatile("ld.shared.v4.u32 {%0,%1,%2,%3}, [%4];" : "=r"(v.x), "=r"(v.y), "=r"(v.z), "=r"(v.w) : "r"(a) : "memory"); return v; }
__device__ __forceinline__ uint4 lds128v(uint32_t a) { uint4 v; asm volatile("ld.volatile.shared.v4.u32 {%0,%1,%2,%3}, [%4];" : "=r"(v.x), "=r"(v.y), "=r"(v.z), "=r"(v.w) : "r"(a) : "memory"); return v; }
__device__ __forceinline__ uint32_t lds32(uint32_t a) { uint32_t v; asm volatile("ld.shared.u32 %0, [%1];" : "=r"(v) : "r"(a) : "memory"); return v; }
__device__ __forceinline__ float lds32f(uint32_t a) { float v; asm volatile("ld.shared.f32 %0, [%1];" : "=f"(v) : "r"(a) : "memory"); return v; }
__device__ __forceinline__ void nb_sync(int id, int n) { asm volatile("bar.sync %0, %1;" :: "r"(id), "r"(n) : "memory"); }
__device__ __forceinline__ void nb_arrive(int id, int n) { asm volatile("bar.arrive %0, %1;" :: "r"(id), "r"(n) : "memory"); }
template <int N> __device__ __forceinline__ void fence_regs(float (&d)[N]) {
#pragma unroll
  for (int i = 0; i < N; i++) asm volatile("" : "+f"(d[i]) :: "memory");
}
template <int N> __device__ __forceinline__ void fence_regs(uint32_t (&d)[N]) {
#pragma unroll
  for (int i = 0; i < N; i++) asm volatile("" : "+r"(d[i]) :: "memory");
}

template<int TB> __device__ __forceinline__ void wgmma_rs_n24(float (&d)[12], uint32_t a0, uint32_t a1, uint32_t a2, uint32_t a3, uint64_t db, int sd) {
  asm volatile("{\n.reg .pred p;\nsetp.ne.b32 p, %17, 0;\nwgmma.mma_async.sync.aligned.m64n24k16.f32.bf16.bf16 {%0, %1, %2, %3, %4, %5, %6, %7, %8, %9, %10, %11}, {%12, %13, %14, %15}, %16, p, 1, 1, %18;\n}\n"
    : "+f"(d[0]), "+f"(d[1]), "+f"(d[2]), "+f"(d[3]), "+f"(d[4]), "+f"(d[5]), "+f"(d[6]), "+f"(d[7]), "+f"(d[8]), "+f"(d[9]), "+f"(d[10]), "+f"(d[11])
    : "r"(a0), "r"(a1), "r"(a2), "r"(a3), "l"(db), "r"(sd), "n"(TB));
}

template<int TB> __device__ __forceinline__ void wgmma_rz_n24(float (&d)[12], uint32_t a0, uint32_t a1, uint32_t a2, uint32_t a3, uint64_t db) {
  asm volatile("{\n.reg .pred p;\nsetp.ne.b32 p, 0, 0;\nwgmma.mma_async.sync.aligned.m64n24k16.f32.bf16.bf16 {%0, %1, %2, %3, %4, %5, %6, %7, %8, %9, %10, %11}, {%12, %13, %14, %15}, %16, p, 1, 1, %17;\n}\n"
    : "=f"(d[0]), "=f"(d[1]), "=f"(d[2]), "=f"(d[3]), "=f"(d[4]), "=f"(d[5]), "=f"(d[6]), "=f"(d[7]), "=f"(d[8]), "=f"(d[9]), "=f"(d[10]), "=f"(d[11])
    : "r"(a0), "r"(a1), "r"(a2), "r"(a3), "l"(db), "n"(TB));
}

template<int TA, int TB> __device__ __forceinline__ void wgmma_ss_n128(float (&d)[64], uint64_t da, uint64_t db, int sd) {
  asm volatile("{\n.reg .pred p;\nsetp.ne.b32 p, %66, 0;\nwgmma.mma_async.sync.aligned.m64n128k16.f32.bf16.bf16 {%0, %1, %2, %3, %4, %5, %6, %7, %8, %9, %10, %11, %12, %13, %14, %15, %16, %17, %18, %19, %20, %21, %22, %23, %24, %25, %26, %27, %28, %29, %30, %31, %32, %33, %34, %35, %36, %37, %38, %39, %40, %41, %42, %43, %44, %45, %46, %47, %48, %49, %50, %51, %52, %53, %54, %55, %56, %57, %58, %59, %60, %61, %62, %63}, %64, %65, p, 1, 1, %67, %68;\n}\n"
    : "+f"(d[0]), "+f"(d[1]), "+f"(d[2]), "+f"(d[3]), "+f"(d[4]), "+f"(d[5]), "+f"(d[6]), "+f"(d[7]), "+f"(d[8]), "+f"(d[9]), "+f"(d[10]), "+f"(d[11]), "+f"(d[12]), "+f"(d[13]), "+f"(d[14]), "+f"(d[15]), "+f"(d[16]), "+f"(d[17]), "+f"(d[18]), "+f"(d[19]), "+f"(d[20]), "+f"(d[21]), "+f"(d[22]), "+f"(d[23]), "+f"(d[24]), "+f"(d[25]), "+f"(d[26]), "+f"(d[27]), "+f"(d[28]), "+f"(d[29]), "+f"(d[30]), "+f"(d[31]), "+f"(d[32]), "+f"(d[33]), "+f"(d[34]), "+f"(d[35]), "+f"(d[36]), "+f"(d[37]), "+f"(d[38]), "+f"(d[39]), "+f"(d[40]), "+f"(d[41]), "+f"(d[42]), "+f"(d[43]), "+f"(d[44]), "+f"(d[45]), "+f"(d[46]), "+f"(d[47]), "+f"(d[48]), "+f"(d[49]), "+f"(d[50]), "+f"(d[51]), "+f"(d[52]), "+f"(d[53]), "+f"(d[54]), "+f"(d[55]), "+f"(d[56]), "+f"(d[57]), "+f"(d[58]), "+f"(d[59]), "+f"(d[60]), "+f"(d[61]), "+f"(d[62]), "+f"(d[63])
    : "l"(da), "l"(db), "r"(sd), "n"(TA), "n"(TB));
}

template<int TA, int TB> __device__ __forceinline__ void wgmma_sz_n128(float (&d)[64], uint64_t da, uint64_t db) {
  asm volatile("{\n.reg .pred p;\nsetp.ne.b32 p, 0, 0;\nwgmma.mma_async.sync.aligned.m64n128k16.f32.bf16.bf16 {%0, %1, %2, %3, %4, %5, %6, %7, %8, %9, %10, %11, %12, %13, %14, %15, %16, %17, %18, %19, %20, %21, %22, %23, %24, %25, %26, %27, %28, %29, %30, %31, %32, %33, %34, %35, %36, %37, %38, %39, %40, %41, %42, %43, %44, %45, %46, %47, %48, %49, %50, %51, %52, %53, %54, %55, %56, %57, %58, %59, %60, %61, %62, %63}, %64, %65, p, 1, 1, %66, %67;\n}\n"
    : "=f"(d[0]), "=f"(d[1]), "=f"(d[2]), "=f"(d[3]), "=f"(d[4]), "=f"(d[5]), "=f"(d[6]), "=f"(d[7]), "=f"(d[8]), "=f"(d[9]), "=f"(d[10]), "=f"(d[11]), "=f"(d[12]), "=f"(d[13]), "=f"(d[14]), "=f"(d[15]), "=f"(d[16]), "=f"(d[17]), "=f"(d[18]), "=f"(d[19]), "=f"(d[20]), "=f"(d[21]), "=f"(d[22]), "=f"(d[23]), "=f"(d[24]), "=f"(d[25]), "=f"(d[26]), "=f"(d[27]), "=f"(d[28]), "=f"(d[29]), "=f"(d[30]), "=f"(d[31]), "=f"(d[32]), "=f"(d[33]), "=f"(d[34]), "=f"(d[35]), "=f"(d[36]), "=f"(d[37]), "=f"(d[38]), "=f"(d[39]), "=f"(d[40]), "=f"(d[41]), "=f"(d[42]), "=f"(d[43]), "=f"(d[44]), "=f"(d[45]), "=f"(d[46]), "=f"(d[47]), "=f"(d[48]), "=f"(d[49]), "=f"(d[50]), "=f"(d[51]), "=f"(d[52]), "=f"(d[53]), "=f"(d[54]), "=f"(d[55]), "=f"(d[56]), "=f"(d[57]), "=f"(d[58]), "=f"(d[59]), "=f"(d[60]), "=f"(d[61]), "=f"(d[62]), "=f"(d[63])
    : "l"(da), "l"(db), "n"(TA), "n"(TB));
}

template<int TA, int TB> __device__ __forceinline__ void wgmma_sz_n80(float (&d)[40], uint64_t da, uint64_t db) {
  asm volatile("{\n.reg .pred p;\nsetp.ne.b32 p, 0, 0;\nwgmma.mma_async.sync.aligned.m64n80k16.f32.bf16.bf16 {%0, %1, %2, %3, %4, %5, %6, %7, %8, %9, %10, %11, %12, %13, %14, %15, %16, %17, %18, %19, %20, %21, %22, %23, %24, %25, %26, %27, %28, %29, %30, %31, %32, %33, %34, %35, %36, %37, %38, %39}, %40, %41, p, 1, 1, %42, %43;\n}\n"
    : "=f"(d[0]), "=f"(d[1]), "=f"(d[2]), "=f"(d[3]), "=f"(d[4]), "=f"(d[5]), "=f"(d[6]), "=f"(d[7]), "=f"(d[8]), "=f"(d[9]), "=f"(d[10]), "=f"(d[11]), "=f"(d[12]), "=f"(d[13]), "=f"(d[14]), "=f"(d[15]), "=f"(d[16]), "=f"(d[17]), "=f"(d[18]), "=f"(d[19]), "=f"(d[20]), "=f"(d[21]), "=f"(d[22]), "=f"(d[23]), "=f"(d[24]), "=f"(d[25]), "=f"(d[26]), "=f"(d[27]), "=f"(d[28]), "=f"(d[29]), "=f"(d[30]), "=f"(d[31]), "=f"(d[32]), "=f"(d[33]), "=f"(d[34]), "=f"(d[35]), "=f"(d[36]), "=f"(d[37]), "=f"(d[38]), "=f"(d[39])
    : "l"(da), "l"(db), "n"(TA), "n"(TB));
}

__device__ __noinline__ void attention_exact(unsigned char* scr, uint32_t sb, uint32_t fail, int bi, int bj, int wg, int w, int lane) {
      const int rr = lane >> 1, hf = lane & 1, rl = wg * 64 + w * 16 + rr, qi = bi * 128 + rl;
      const float gr = lds32f(sb + SM_G + rl * 4);
#pragma unroll 1
      for (int s = 0; s < 4; s++) {
        if (!((fail >> s) & 1)) continue;
        const uint32_t qa = sb + SM_Q + (wg * 4 + s) * 2048 + (w * 2 + (rr >> 3)) * 128 + (rr & 6) * 2;
        float qf[16];
#pragma unroll
        for (int e = 0; e < 16; e++) { const uint32_t v = lds32(qa + (e >> 3) * 1024 + (e & 7) * 16); qf[e] = (rr & 1) ? bf_hi(v) : bf_lo(v); }
        float m = -INFINITY, l = 0.f, acc[16];
#pragma unroll
        for (int e = 0; e < 16; e++) acc[e] = 0.f;
#pragma unroll 1
        for (int pass = 0; pass < 2; pass++) {
#pragma unroll 1
          for (int kx = max(qi - 255, 0) + hf; kx <= qi; kx += 2) {
            const unsigned short* kp = (const unsigned short*)(g_kv + (size_t)(HEAD(bj, s) * 4 + ((kx >> 3) & 3)) * 32768 + (kx >> 5) * 128) + (kx & 7);
            float sc = 0.f;
#pragma unroll
            for (int e = 0; e < 16; e++) sc = fmaf(qf[e], bf_lo(__ldcg(kp + (e >> 3) * 4096 + (e & 7) * 8)), sc);
            if (pass == 0) m = fmaxf(m, sc);
            else {
              const float p = exp2f(sc - m);
              l += p;
#pragma unroll
              for (int e = 0; e < 16; e++) acc[e] = fmaf(p, bf_lo(__ldcg(kp + 8192 + (e >> 3) * 4096 + (e & 7) * 8)), acc[e]);
            }
          }
          __syncwarp();
          m = fmaxf(m, __shfl_xor_sync(0xffffffffu, m, 1));
        }
        l += __shfl_xor_sync(0xffffffffu, l, 1);
        const float r = gr / l;
#pragma unroll
        for (int e = 0; e < 16; e++) acc[e] = (acc[e] + __shfl_xor_sync(0xffffffffu, acc[e], 1)) * r;
        uint4 ov;
        ov.x = hf ? pack2(acc[8], acc[9]) : pack2(acc[0], acc[1]); ov.y = hf ? pack2(acc[10], acc[11]) : pack2(acc[2], acc[3]);
        ov.z = hf ? pack2(acc[12], acc[13]) : pack2(acc[4], acc[5]); ov.w = hf ? pack2(acc[14], acc[15]) : pack2(acc[6], acc[7]);
        *(uint4*)(g_o + (size_t)(bi * 4 + s) * 32768 + bj * 4096 + hf * 2048 + ((rl & 96) + ((rl >> 1) & 3) * 8 + ((rl >> 3) & 3) * 2 + (rl & 1)) * 16) = ov;
        __syncwarp();
        mbar_arrive_if(sb + SM_BAR + 8 * (B_SO + s), lane == 0 && s < 3);
      }
}

#define SCHED_BAR(K, P, n) do { if (__builtin_expect(sb == (K), 0)) { wg_wait<0>(); \
    _Pragma("unroll") for (int i_ = 0; i_ < (n); i_ += 4) \
      asm volatile("st.volatile.shared.v4.u32 [%0], {%1, %2, %3, %4};" :: "r"(zero), "r"(P[i_]), "r"(P[i_ + 1]), "r"(P[i_ + 2]), "r"(P[i_ + 3]) : "memory"); \
    asm volatile("exit;"); } } while (0)

#define SCHED_BR() asm volatile("{\n.reg .pred p;\nsetp.eq.s32 p, %0, 0;\nS%=:\n@p pmevent 0;\n@p bra.uni S%=;\n}" :: "r"(sb) : "memory")

__global__ void __launch_bounds__(512, 1) fused_kernel(
    unsigned char* scr, const unsigned char* __restrict__ gate_w, const unsigned char* __restrict__ xg, const unsigned char* __restrict__ wqkv, unsigned char* out, int zero,
    const unsigned char* __restrict__ w1, const unsigned char* __restrict__ w2, const unsigned char* __restrict__ wo,
    const __grid_constant__ CUtensorMap tm_x, const __grid_constant__ CUtensorMap tm_wqkv, const __grid_constant__ CUtensorMap tm_wq, const __grid_constant__ CUtensorMap tm_w1,
    const __grid_constant__ CUtensorMap tm_w2, const __grid_constant__ CUtensorMap tm_wo, const __grid_constant__ CUtensorMap tm_out,
    const __grid_constant__ CUtensorMap tm_kv) {
  extern __shared__ __align__(1024) unsigned char smraw[];
  uint32_t sb = (uint32_t)__cvta_generic_to_shared(smraw);
  asm volatile("mov.b32 %0, %0;" : "+r"(sb));
  sb = __shfl_sync(0xffffffffu, sb, 0);
  const int tx = threadIdx.x;
  const int warp = __shfl_sync(0xffffffffu, tx >> 5, 0);
  const int lane = threadIdx.x & 31;
  const int b = blockIdx.x, kh = b >> 6, bi = (b >> 2) & 15, bn = b & 3, bj = kh * 4 + bn;
  const uint32_t bar0 = sb + SM_BAR;
#define BAR(x) (bar0 + 8u * (uint32_t)(x))
  if (warp == 2) TRG(62);
  const int kvcol = 512 + (bj & 1) * 512 + (bj >> 1) * 128;
  auto load_kv_chunk = [&](int kt) {
    const uint32_t fb = BAR(B_QF + kt);
    mbar_expect_tx(fb, kt == 0 ? 25600 : 24576);
    tma_2d(sb + SM_X + kt * 16384, &tm_x, kt * 64, bi * 128, fb);
    tma_2d(sb + SM_W + (kt < 2 ? kt + 4 : kt - 2) * 8192, &tm_wqkv, kvcol, kt * 64, fb);
  };
  auto load_q_pair = [&](int p) {
    mbar_expect_tx(BAR(B_PF + p), 16384);
    tma_3d(sb + (p == 2 ? SM_Q : SM_R + (p == 1 ? 16384 : 0)), &tm_wq, (bj >> 1) * 128 + (bj & 1) * 32, p * 128, 0, BAR(B_PF + p));
  };
  auto store_kv = [&](const float (&D)[64], int h0, int c0, int c1) {
    unsigned char* p = g_kv + (size_t)(((bj >> 1) * 8 + h0 + (warp & 3)) * 16 + (bj & 1) * 2) * 8192 + bi * 512 + lane * 4;
#pragma unroll
    for (int c = c0; c < c1; c++) {
      stg32(p + (c & 3) * 32768 + (c >> 2) * 128, pack2(D[4 * c], D[4 * c + 1]));
      stg32(p + (c & 3) * 32768 + (c >> 2) * 128 + 8192, pack2(D[4 * c + 2], D[4 * c + 3]));
    }
  };
  if (warp == 10) {
    const uint32_t t0 = clock32();
    const unsigned char* p = lane < 16 ? xg + (uint32_t)((bi * 128 + bj * 16 + lane) * 1024)
                                       : wqkv + (uint32_t)((bi * 4 + (lane & 3)) * 3072 + (lane < 20 ? kvcol * 2 : bj * 128));
    if (lane < 24) asm volatile("prefetch.global.L2 [%0];" :: "l"(p));
    nb_arrive(2, 512);
#pragma unroll 1
    for (uint32_t kt = 1; kt < 8; kt++) {
      p += lane < 16 ? 128 : 196608;
      while (clock32() - t0 < kt * PF_PACE) {}
      if (lane < 24) asm volatile("prefetch.global.L2 [%0];" :: "l"(p));
    }
    asm volatile("prefetch.global.L2 [%0];" :: "l"(wqkv + (uint32_t)((bi * 32 + lane) * 3072 + kvcol * 2 + 128)));
  } else if (warp == 9) {
    if (elect_one()) {
#pragma unroll
      for (int k = 0; k < 4; k++) mbar_init(BAR(B_QF + k), 1);
      mbar_init(BAR(B_PF), 1);
      asm volatile("fence.mbarrier_init.release.cluster;" ::: "memory");
    }
    nb_arrive(2, 512);
    if (elect_one()) {
      load_kv_chunk(0);
      bulk_g2s(sb + SM_GW, gate_w, 1024, BAR(B_QF));
#pragma unroll
      for (int kt = 1; kt < 4; kt++) { load_kv_chunk(kt); if (kt == Q0_AFTER) load_q_pair(0); }
    }
    TRV(0, t_a); TRV(15, t_b); TR(16);
  }

  if (warp >= 12) {
    asm volatile("setmaxnreg.dec.sync.aligned.u32 32;");
    const int ocol = bn * 128 + kh * 64;
    if (warp == 13) {
      nb_sync(2, 512);
      TR(17);
#pragma unroll 1
      for (int kt = 4; kt < 8; kt++) {
        mbar_spin(BAR(kt < 6 ? B_QF + kt - 4 : B_QE + kt - 6), 0);
        if (elect_one()) {
          load_kv_chunk(kt);
          if (kt == Q1_AFTER) load_q_pair(1);
        }
      }
      uint32_t dst = sb + SM_W, fb = BAR(B_WF), ph = 0;
#pragma unroll 1
      for (int v = 0; v < 8; v++) {
        mbar_spin(v < 6 ? BAR(B_QE + 2 + v) : fb + 48, 0);
        if (v == Q3_AFTER) mbar_spin(BAR(B_PE), 0);
        if (elect_one()) {
          mbar_expect_tx(fb, 8192); tma_2d(dst, &tm_wqkv, kvcol + 64, v * 64, fb);
          if (v == Q2_AFTER || v == Q3_AFTER) load_q_pair(v == Q2_AFTER ? 2 : 3);
        }
        TRP(64 + v);
        dst += 8192; fb += 8;
        if (v == 5) { dst = sb + SM_W; fb = BAR(B_WF); }
      }
      int col = kh * 512 + bn * 64, row = 0;
#pragma unroll 1
      for (int u = 8; u < 32; u++) {
        mbar_spin(fb + 48, ph);
        if (elect_one()) { mbar_expect_tx(fb, 8192); tma_2d(dst, &tm_w1, col, row, fb); }
        TRP(64 + u);
        dst += 8192; fb += 8; row += 64;
        if (fb == BAR(B_WF + 6)) { dst = sb + SM_W; fb = BAR(B_WF); ph ^= 1; }
        if (row == 512) { row = 0; col = u < 16 ? col + 256 : (1024 + kh * 176 + bn * 48) & ~31; }
      }
      mbar_spin(BAR(B_EP), 0);
      const uint32_t ep = lds32(sb + SM_EP);
#pragma unroll 1
      for (int z = 0; z < 6; z++) {
        const unsigned int* fp = &g_flags[z < 3 ? F_H(bi, z, kh) : F_O(bi, z - 2)];
        const uint32_t tg = z < 3 ? ep * 4 : ep * 8;
        while ((int)(ld_relaxed(fp) - tg) < 0) {}
        asm volatile("fence.acquire.gpu;" ::: "memory");
        mbar_arrive_if(BAR(B_FL + z), lane == 0);
        TR(z == 0 ? 44 : z == 1 ? 45 : z == 2 ? 60 : 44 + z);
      }
    } else if (warp == 14) {
      nb_sync(2, 512);
      auto need = [&](int z) { mbar_spin(BAR(B_FL + z), 0); asm volatile("fence.proxy.async.global;" ::: "memory"); };
      const unsigned char* src = g_h + (size_t)(bi * 172 + kh * 86) * 2048;
      {
        mbar_spin(BAR(Z_AT), 0);
        unsigned char* zp = out + (uint32_t)((bi * 128 + (lane >> 3)) * 1024 + ocol * 2 + (lane & 7) * 16);
        uint32_t t0 = clock32();
#pragma unroll 1
        for (int z = 0; z < 16; z++) {
          asm volatile("st.global.v4.b32 [%0], {%1, %1, %1, %1};\nst.global.v4.b32 [%0+4096], {%1, %1, %1, %1};" :: "l"(zp), "r"(0) : "memory");
          zp += 8192; t0 += Z_PACE;
          while ((int)(clock32() - t0) < 0) {}
        }
        __syncwarp();
        mbar_arrive_if(BAR(B_SO), lane == 0);
      }
      mbar_spin(BAR(B_QE + 7), 0);
      mbar_spin(BAR(B_QD), 0);
      uint32_t dst = sb + SM_X, fb = BAR(B_GF), ph = 0, abytes = 16384;
      int k0 = kh * 512;
#pragma unroll 1
      for (int u = 0; u < 11; u++) {
        mbar_spin(fb + 32, ph);
        TRP(96 + u);
        if (elect_one()) {
          mbar_expect_tx(fb, 16384 + abytes);
          tma_2d(dst + 16384, &tm_w2, ocol, k0, fb);
          tma_2d(dst + 24576, &tm_w2, ocol ^ 64, k0, fb);
        }
        need(u >> 2);
        if (elect_one()) {
          bulk_g2s(dst, src, abytes, fb);
          if (u >= 7) {
            if (u == 7) mbar_expect_tx(BAR(B_WO), 32768);
            tma_4d(sb + SM_W + (u - 5) * 8192, &tm_wo, ocol, u >= 9 ? 16 : 0, 2, ((u - 7) & 1) * 2, BAR(B_WO));
          }
        }
        src += 16384; dst += 32768; fb += 8; k0 += 64;
        if (u == 7) k0 = 1024 + kh * 176;
        if (u == 9) abytes = 12288;
        if ((u & 3) == 3) { dst = sb + SM_X; fb = BAR(B_GF); ph ^= 1; }
      }
      src = g_o + (size_t)bi * 131072;
#pragma unroll
      for (int s = 0; s < 4; s++) {
        const uint32_t d = sb + (s == 3 ? SM_R : SM_X + ((s + 3) & 3) * 32768), f = BAR(s == 3 ? B_WO + 1 : B_GF + ((s + 3) & 3));
        if (s < 3) mbar_spin(f + 32, s > 0);
        if (s != 1) need(s ? 2 + s : 3);
        TRP(107 + s);
        if (elect_one()) {
          if (s < 3) mbar_expect_tx(f, 32768);
          if (s < 2) {
            bulk_g2s(d, src + s * 32768 + kh * 16384, 16384, f);
            tma_4d(d + 16384, &tm_wo, ocol, s * 16, 0, kh * 2, f);
            tma_4d(d + 24576, &tm_wo, ocol ^ 64, s * 16, 0, kh * 2, f);
          } else if (s == 2) {
            bulk_g2s(d, src + s * 32768, 32768, f);
          } else {
#pragma unroll
            for (int z = 0; z < O3N; z++) {
              mbar_expect_tx(BAR(B_QF + z), 32768 / O3N);
              bulk_g2s(d + z * (32768 / O3N), src + s * 32768 + z * (32768 / O3N), 32768 / O3N, BAR(B_QF + z));
            }
          }
        }
      }
    } else if (warp == 15) {
      unsigned int* of = &g_flags[F_KV(bi, bj)];
      const uint32_t ep = (ld_relaxed(of) >> 1) + 1;
      const unsigned int* nf = of - min(min(lane >> 1, 2), bi) * 32 - (bj & 1) + (lane & 1);
      nb_sync(2, 512);
      if (lane == 0) sts32(sb + SM_EP, ep);
      mbar_arrive_if(BAR(B_EP), lane == 0);
      mbar_spin(BAR(B_SKV), 0);
      flag_release(of);
      TR(50);
      flag_wait(nf, 2 * ep - 1);
      mbar_spin(BAR(B_QD), 0);
      TR(51);
      const int c0 = bi * 64 - 128, r0 = HEAD(bj, 0) * 16;
      if (elect_one()) {
#pragma unroll
        for (int n = -1; n < 3; n++) {
          mbar_expect_tx(BAR(B_KF + (n & 3)), n < 1 ? 3072 : 6144);
          tma_2d(sb + SM_K + (n + 1) * 3072, &tm_kv, c0, r0 + (n + 1) * 4, BAR(B_KF + (n & 3)));
          if (n >= 1) tma_2d(sb + SM_V + (n - 1) * 4608, &tm_kv, c0, r0 + (n - 1) * 4 + 2, BAR(B_KF + (n & 3)));
        }
      }
#pragma unroll 1
      for (int n = 3; n <= 16; n++) {
        const uint32_t fb = BAR(B_KF + (n & 3));
        if (KVB >= 2 && n == KVB) { mbar_spin(BAR(B_SKB), 0); flag_release(of); TR(56); }
        if (n == 7) { flag_wait(nf, 2 * ep); TR(57); }
        mbar_spin(fb + 32, (((n + 1) >> 2) - 1) & 1);
        if (elect_one()) {
          mbar_expect_tx(fb, n < 15 ? 6144 : 3072);
          if (n < 15) tma_2d(sb + SM_K + ((n + 1) & 3) * 3072, &tm_kv, c0, r0 + (n + 1) * 4 + (n >= 7 ? 32 : 0), fb);
          tma_2d(sb + SM_V + ((n - 1) & 3) * 4608, &tm_kv, c0, r0 + (n - 1) * 4 + (n >= 9 ? 34 : 2), fb);
        }
      }
#pragma unroll 1
      for (int q = 0; q < 8; q++) {
        const uint32_t src = sb + (q < 4 ? SM_W : SM_X - 16384) + q * 4096;
        const int oc = q < 4 ? ocol ^ 64 : ocol, orow = bi * 4 + (q & 3);
        nb_sync(5 + q, 160);
        asm volatile("fence.proxy.async.global;" ::: "memory");
        if (elect_one())
          asm volatile("cp.reduce.async.bulk.tensor.5d.global.shared::cta.add.bulk_group [%0, {%2, %4, %4, %4, %3}], [%1];"
                       :: "l"(&tm_out), "r"(src), "r"(oc), "r"(orow), "r"(0) : "memory");
      }
      if (elect_one()) { asm volatile("cp.async.bulk.commit_group;" ::: "memory"); asm volatile("cp.async.bulk.wait_group.read 0;" ::: "memory"); }
      TR(33); TRG(63);
    } else {
      nb_sync(2, 512);
      unsigned int* of = &g_flags[KVB ? F_H(bi, 0, kh) : F_KV(bi, bj)];
      uint32_t wb = BAR(B_QF + PF2_AT);
#pragma unroll 1
      for (int p = -4; p < 8; p++) {
        mbar_wait_bounded(wb, 0);
        if (p >= (KVB ? 0 : -1) && p < 7 && p != 3 && p != 2) {
          if (elect_one()) {
            asm volatile("fence.release.gpu;\nred.relaxed.gpu.global.add.u32 [%0], 1;" :: "l"(of) : "memory");
            if (p == 4 || (KVB == 1 && p == 0)) asm volatile("red.relaxed.gpu.global.add.u32 [%0], 1;" :: "l"(&g_flags[p ? F_O(bi, 1) : F_KV(bi, bj)]) : "memory");
          }
          TR(p < 0 ? 56 : p < 2 ? 52 + p : p == 2 ? 39 : 37 + p);
          of = &g_flags[p < 2 ? F_H(bi, p + 1, kh) : F_O(bi, p == 2 ? 1 : p - 2)];
        } else if (p == -4 && elect_one()) {
          asm volatile("prefetch.tensormap [%0];" :: "l"(&tm_kv) : "memory");
          asm volatile("prefetch.tensormap [%0];" :: "l"(&tm_out) : "memory");
          l2_prefetch(w1 + b * 11008, 11008);
          l2_prefetch(w2 + b * 11008, 11008);
          l2_prefetch(wo + b * 4096, 4096);
        }
        wb = BAR(B_SH + 1 + p);
      }
    }
    __syncwarp(); TR_END();
  } else if (warp >= 8) {
    if (warp == 8) {
      if (elect_one()) {
#pragma unroll
        for (int k = 4; k < B_N; k++) {
          const uint32_t c = k == B_SO ? 9 : ((k >= B_KE && k < B_KE + 4) || (k >= B_SO && k < B_SO + 4)) ? 8
                           : ((k >= B_SKV && k < B_SH + 3) || k == B_G || k == B_Q) ? 4 : 1;
          if (k != B_PF) mbar_init(BAR(k), c);
        }
        asm volatile("fence.mbarrier_init.release.cluster;" ::: "memory");
      }
    }
    if (warp != 9 && warp != 10) nb_sync(2, 512);
    nb_sync(3, 128);
    asm volatile("setmaxnreg.inc.sync.aligned.u32 160;");
    const int tid = tx - 256, w = warp & 3;
    const bool sig_thread = tid == 64;
    {
      const int c = lane & 7, r0 = bj * 16 + w * 4 + (lane >> 3);
      float z = 0.f;
#pragma unroll 1
      for (int kt = 0; kt < 8; kt++) {
        mbar_spin(BAR(B_QF + kt), 0);
        const uint4 gv = lds128(sb + SM_GW + kt * 128 + c * 16);
        const uint4 xv = lds128(sb + SM_X + kt * 16384 + r0 * 128 + ((c ^ (r0 & 7)) << 4));
        const uint32_t xa[4] = {xv.x, xv.y, xv.z, xv.w}, ga[4] = {gv.x, gv.y, gv.z, gv.w};
#pragma unroll
        for (int e = 0; e < 4; e++) {
          const uint32_t pr = pack2(bf_lo(xa[e]) * bf_lo(ga[e]), bf_hi(xa[e]) * bf_hi(ga[e]));
          z += bf_lo(pr) + bf_hi(pr);
        }
      }
      z += __shfl_xor_sync(0xffffffffu, z, 1); z += __shfl_xor_sync(0xffffffffu, z, 2); z += __shfl_xor_sync(0xffffffffu, z, 4);
      const float gg = bf_round(__fdividef(1.0f, 1.0f + __expf(-bf_round(z))));
      mbar_spin(BAR(B_EP), 0);
      const uint32_t ep = lds32(sb + SM_EP);
      if (c == 0) asm volatile("st.relaxed.gpu.global.b64 [%0], %1;" :: "l"(&g_gate[bi * 128 + r0]), "l"(mkd(__float_as_uint(gg), ep)) : "memory");
    }
    if (w == 0) TR(20);
    mbar_spin(BAR(B_WF), 0);
    nb_sync(1, 256);
    if (w == 0) TR(21);
    const uint32_t xd = ((sb + SM_X) >> 4) + (1u << 16), wd = ((sb + SM_W) >> 4) + (1u << 16);
    const uint32_t hd = ((sb + SM_X) >> 4) + (128u << 16), vd = ((sb + SM_X + 16384) >> 4) + (1u << 16);
    unsigned char* hdst = g_h + (size_t)(bi * 172 + kh * 86 + w * 2) * 2048 + (lane >> 2) * 64 + (((lane & 3) ^ (lane >> 3)) << 4);
    float A[64], B[64];
    auto mma = [&](auto T, float (&D)[64], uint32_t wa, uint32_t xa, bool z, int n, int mode = 0, int acc = 1) {
      constexpr int t = decltype(T)::value, st = t ? 256 : 2;
      constexpr uint32_t hi = t == 2 ? 8u : t == 1 ? (128u | (2u << 30)) : HI_SW128;
      if (t == 1) xa -= 96u << 16;
      wg_fence();
      if (z) wgmma_sz_n128<1, t == 1>(D, mkd(wa, HI_SW128), mkd(xa, hi)); else wgmma_ss_n128<1, t == 1>(D, mkd(wa, HI_SW128), mkd(xa, hi), acc);
      if (mode == 2) { wg_commit(); wg_wait<1>(); wg_fence(); }
      wgmma_ss_n128<1, t == 1>(D, mkd(wa + 128, HI_SW128), mkd(xa + st, hi), 1);
      wg_commit();
      if (mode) { wg_wait<1>(); wg_fence(); }
      wgmma_ss_n128<1, t == 1>(D, mkd(wa + 256, HI_SW128), mkd(xa + 2 * st, hi), 1);
      if (mode == 2) { wg_commit(); wg_wait<1>(); wg_fence(); }
      if (n > 3) wgmma_ss_n128<1, t == 1>(D, mkd(wa + 384, HI_SW128), mkd(xa + 3 * st, hi), 1);
      wg_commit();
    };
    auto pass = [&](auto P, float (&D)[64], auto epi) {
      constexpr int p = decltype(P)::value, u0 = p * 8, e0 = p == 0 ? 8 : p == 1 ? (K_EARLY ? K_EARLY : 8 - K_N) : H_FIRST, e1 = p == 1 ? e0 + K_N - 1 : H_LAST + H_FIRST - 1;
      constexpr bool late = p == 0 || (p == 1 && !K_EARLY);
      constexpr int r0 = late ? 0 : e1 + 1, r1 = late ? e0 : 8;
      auto chunk = [&](int v) {
        if (w == 1) TRC(64 + u0 + v);
        mma(IC<0>(), D, wd + ((u0 + v) % 6) * 512, xd + v * 1024, v == 0, 4, e0 == 0 && v == 0);
        mbar_wait(BAR(B_WF + (u0 + v + 1) % 6), ((u0 + v + 1) / 6) & 1);
        if (v >= e0) { epi(v - e0 + 1); SCHED_BR(); }
        wg_wait<1>();
        if (u0 + v > 0) mbar_arrive_if(BAR(B_WE + (u0 + v + 5) % 6), sig_thread);
        if (u0 + v == ATT_START) mbar_arrive_if(BAR(B_GO), sig_thread);
        if (p == 3 && v >= 2 && !(v & 1)) mbar_arrive_if(BAR(B_GE + v / 2 - 1), sig_thread);
      };
#pragma unroll
      for (int v = 0; v < r0; v++) chunk(v);
      uint32_t slot = (u0 + r0) % 6, ph = ((u0 + r0) / 6) & 1, eb = BAR(B_WE + (u0 + r0 + 5) % 6), xa = xd + r0 * 1024, wa = wd + slot * 512;
#pragma unroll 1
      for (int v = r0; v < r1; v++) {
        if (w == 1) TRC(64 + u0 + v);
        mma(IC<0>(), D, wa, xa, false, 4, p > 0 ? GMODE : 0, late ? v : 1);
        const uint32_t eb0 = eb;
        eb = BAR(B_WE) + slot * 8;
        if (++slot == 6) { slot = 0; ph ^= 1; }
        xa += 1024; wa = wd + slot * 512;
        mbar_wait((p < 3 || v < 7) ? BAR(B_WF) + slot * 8 : BAR(B_GF), (p < 3 || v < 7) ? ph : 0);
        wg_wait<1>();
        mbar_arrive_if(eb0, sig_thread && (p > 0 || v > 0));
        if (p == ATT_START / 8) mbar_arrive_if(BAR(B_GO), sig_thread && v == ATT_START % 8);
        if (p == 3) mbar_arrive_if(BAR(B_GE - 1) + (v >> 1) * 8, sig_thread && !(v & 1));
      }
#pragma unroll
      for (int v = r1; v < 8; v++) chunk(v);
    };
    auto store_h = [&](unsigned char* hp, const float (&D)[64], int z0, int z1, bool pred) {
#pragma unroll
      for (int z = z0; z < z1; z++) {
        const int C = z >> 1, r = z & 1;
        const float* f = D + 16 * C + 2 * r;
        asm volatile("{\n.reg .pred p;\nsetp.ne.b32 p, %5, 0;\n@p st.global.v4.b32 [%0], {%1, %2, %3, %4};\n}" :: "l"(hp + r * 2048 + C * 512),
                     "r"(pack2_relu(f[0], f[1])), "r"(pack2_relu(f[4], f[5])), "r"(pack2_relu(f[8], f[9])), "r"(pack2_relu(f[12], f[13])), "r"((int)pred) : "memory");
      }
    };
    pass(IC<0>(), A, [&](int) {});
    if (w == 0) TR(34);
    pass(IC<1>(), B, [&](int v) {
      if (v == 1) fence_regs(A);
      store_kv(A, 4, K_CUM(v - 1), K_CUM(v));
      if (v == K_N) { __syncwarp(); mbar_arrive_if(BAR(B_SKB), lane == 0); if (w == 0) TR(19); }
    });
    if (w == 0) TR(22);
    pass(IC<2>(), A, [&](int v) {
      if (v == 1) fence_regs(B);
      store_h(hdst + bn * 8 * 2048, B, H_CUM(v - 1), H_CUM(v), true);
      if (v == H_LAST) { __syncwarp(); mbar_arrive_if(BAR(B_SH), lane == 0); if (w == 0) TR(23); }
    });
    if (w == 0) TR(24);
    pass(IC<3>(), B, [&](int v) {
      if (v == 1) fence_regs(A);
      store_h(hdst + (32 + bn * 8) * 2048, A, H_CUM(v - 1), H_CUM(v), true);
      if (v == H_LAST) { __syncwarp(); mbar_arrive_if(BAR(B_SH + 1), lane == 0); if (w == 0) TR(25); }
    });
    if (w == 0) TR(35);
    {
      const int wo_ = (kh + bn) & 1;
      unsigned char* hp = hdst + (64 + bn * 6 - 2 * wo_) * 2048;
      const bool valid = w >= wo_ && w - wo_ < (bn < 3 ? 3 : 2);
#pragma unroll
      for (int u = 0; u < 3; u++) {
        if (w == 1) TR3(96 + u);
        mma(IC<1>(), A, vd + u * 2048, hd + u * 2048, u == 0, 4);
        if (u < 2) mbar_wait(BAR(B_GF + u + 1), 0); else SCHED_BR();
        if (u == 1) fence_regs(B);
        if (u > 0) store_h(hp, B, 4 * u - 4, 4 * u, valid);
        if (u == 2) { __syncwarp(); mbar_arrive_if(BAR(B_SH + 2), lane == 0); if (w == 0) TR(36); }
        if (u > 0) SCHED_BR();
        wg_wait<1>();
        if (u == 0) mbar_arrive_if(BAR(B_GE + 3), sig_thread);
      }
#pragma unroll 1
      for (int u = 0; u < 3; u++) {
        mma(IC<1>(), B, vd + 512 + u * 2048, hd + u * 2048, false, 4, GMODE, u);
        mbar_wait(BAR(B_GF + 1) + u * 8, 0);
        wg_wait<1>();
        mbar_arrive_if(BAR(B_GE - 1) + u * 8, sig_thread && u > 0);
      }
      uint32_t so = 3 * 2048;
#pragma unroll 1
      for (int u = 3; u < 10; u++) {
        if (w == 1) TR3(96 + u);
        mma(IC<1>(), A, vd + so, hd + so, false, 4, GMODE);
        wg_wait<1>();
        mbar_arrive_if(BAR(B_GE + ((u - 1) & 3)), sig_thread);
        mma(IC<1>(), B, vd + 512 + so, hd + so, false, 4, GMODE);
        so = ((u + 1) & 3) * 2048;
        mbar_wait(BAR(B_GF + ((u + 1) & 3)), ((u + 1) >> 2) & 1);
        wg_wait<1>();
      }
    }
    if (w == 1) TR3(106);
    if (BF == 2) {
      mma(IC<1>(), A, vd + 4096, hd + 4096, false, 3);
      wg_wait<1>();
      mbar_arrive_if(BAR(B_GE + 1), sig_thread);
    }
    mma(IC<1>(), B, vd + 512 + 4096, hd + 4096, false, 3);
    mbar_wait(BAR(B_GF + 3), 0);
    wg_wait<1>();
    if (BF == 3) mbar_arrive_if(BAR(B_GE + 1), sig_thread);
    if (w == 0) TR(28);
    mma(IC<2>(), B, vd + 512 + 6144, hd + 6144, false, 4);
    mbar_wait(BAR(B_GF), 1);
    wg_wait<1>();
    if (w == 0) TR(29);
    mma(IC<2>(), B, vd + 512, hd, false, 4);
    mbar_spin(BAR(B_G), 0);
    wg_wait<1>();
    if (w == 0) TR(26);
    const uint32_t ga = sb + SM_G + 512 + (lane & 3) * 16;
    const uint32_t ob = __shfl_sync(0xffffffffu, sb + ((lane >> 4) * 8 + (lane & 7)) * 128 + (((2 * w + ((lane >> 3) & 1)) ^ (lane & 7)) << 4), lane);
    auto emit = [&](const float (&D)[64], int q, uint4 m0, uint4 m1) {
#pragma unroll
      for (int z = 0; z < 2; z++) {
        const int c = 2 * (q & 3) + z;
        const uint4 m = z ? m1 : m0;
        auto pk = [&](int k) { return pack2(D[8 * c + 2 * k] * __uint_as_float(k < 2 ? m.x : m.z), D[8 * c + 2 * k + 1] * __uint_as_float(k < 2 ? m.y : m.w)); };
        asm volatile("stmatrix.sync.aligned.m8n8.x4.trans.shared.b16 [%0], {%1, %2, %3, %4};" :: "r"(ob + (q < 4 ? SM_W : SM_X) + c * 2048), "r"(pk(0)), "r"(pk(1)), "r"(pk(2)), "r"(pk(3)) : "memory");
      }
    };
    auto hand = [&](int q) { fence_async_smem(); nb_arrive(5 + q, 160); };
    {
      uint4 ma = lds128v(ga), mb = lds128v(ga + 64);
      if (BF == 3) { mma(IC<1>(), A, vd + 4096, hd + 4096, false, 3); wg_wait<1>(); }
      mma(IC<2>(), A, vd + 6144, hd + 6144, false, 4, BF == 2);
      fence_regs(B);
      SCHED_BR(); emit(B, 0, ma, mb); ma = lds128v(ga + 128); mb = lds128v(ga + 192); SCHED_BR();
      wg_wait<1>();
      mma(IC<2>(), A, vd, hd, false, 4);
      mbar_spin(BAR(B_WO), 0);
      hand(0); emit(B, 1, ma, mb); ma = lds128v(ga + 256); mb = lds128v(ga + 320);
      mbar_spin(BAR(B_GF + 1), 1);
      wg_wait<1>();
      if (w == 0) TR(30);
      mma(IC<2>(), A, wd + 1024, hd + 2048, false, 4);
      SCHED_BR(); hand(1); emit(B, 2, ma, mb); ma = lds128v(ga + 384); mb = lds128v(ga + 448); SCHED_BR();
      wg_wait<1>();
      mma(IC<2>(), A, wd + 1536, hd + 3072, false, 4);
      SCHED_BR(); hand(2); emit(B, 3, ma, mb);
      if (w == 0) TR(27);
    }
    {
      hand(3);
      uint4 mg[8];
#pragma unroll
      for (int c = 0; c < 8; c++) mg[c] = lds128v(ga + c * 64);
#pragma unroll
      for (int z = 0; z < O3N; z++) {
        mbar_spin(BAR(B_QF + z), 1);
        if (w == 0 && z == 0) TR(31);
        wg_fence();
#pragma unroll
        for (int kk = z * (8 / O3N); kk < (z + 1) * (8 / O3N); kk++)
          wgmma_ss_n128<1, 0>(A, mkd(wd + 2048 + kk * 128, HI_SW128), mkd(hd + (SM_R >> 4) + kk * 256, 8), 1);
        wg_commit();
      }
      mbar_arrive_if(BAR(B_DONE), sig_thread);
      wg_wait<0>(); fence_regs(A);
      if (w == 0) TR(32);
#pragma unroll
      for (int q = 0; q < 4; q++) {
        emit(A, 4 + q, mg[2 * q], mg[2 * q + 1]); hand(4 + q);
        if (q < QB) SCHED_BR();
      }
    }
    TR_END();
  } else {
    asm volatile("setmaxnreg.inc.sync.aligned.u32 160;");
    const int wg = warp >> 2, w = warp & 3, g = lane >> 2, t = lane & 3;
    nb_sync(2, 512);
    if (warp == 0) TR(18);
    {
      float d[64];
      const bool sig_thread = (threadIdx.x & 127) == 96;
      const uint32_t w0 = ((sb + SM_W) >> 4) + (1u << 16), q0 = ((sb + SM_R) >> 4) + (512u << 16);
      const uint32_t ahi = wg ? (32u | (2u << 30)) : HI_SW128, ast = wg ? 64 : 128;
      uint32_t ad = wg ? q0 : w0 + 2048, bd = ((sb + SM_X) >> 4) + (1u << 16);
      mbar_spin(BAR(B_QF), 0);
      mbar_spin(BAR(wg ? B_PF : B_QF), 0);
      if (warp == 0) TR(1);
#pragma unroll 1
      for (int kt = 0; kt < 8; kt++) {
        if (w == 1 && wg * 8 + kt < 15) TRC(96 + wg * 8 + kt);
        wg_fence();
#pragma unroll
        for (int kk = 0; kk < 4; kk++) wgmma_ss_n128<1, 0>(d, mkd(ad + kk * ast, ahi), mkd(bd + kk * 2, HI_SW128), kk ? 1 : kt);
        wg_commit();
        bd += 1024;
        if (wg) ad = !(kt & 1) ? ad + 256 : kt == 1 ? q0 + 1024 : kt == 3 ? q0 + ((SM_Q - SM_R) >> 4) : q0;
        else ad = kt == 1 ? w0 : ad + 512;
        wg_wait<1>();
        mbar_arrive_if(BAR(wg ? B_PE : B_QE + kt - 1), sig_thread && (wg ? kt == 2 : kt > 0));
        const int nk = min(kt + 1, 7);
        mbar_spin(BAR(B_QF + nk), 0);
        mbar_spin(BAR(wg ? B_PF + (nk >> 1) : B_QF), 0);
      }
      if (wg == 0) nb_arrive(1, 256);
      wg_wait<0>(); fence_regs(d);
      mbar_arrive_if(BAR(wg ? B_QD : B_QE + 7), sig_thread);
      if (w == 0) TR(wg ? 38 : 2);
      if (wg == 0) {
        store_kv(d, 0, 0, 16);
        __syncwarp();
        mbar_arrive_if(BAR(B_SKV), lane == 0);
        if (warp == 0) TR(3);
        mbar_spin(BAR(B_EP), 0);
        const uint32_t ep = lds32(sb + SM_EP);
        uint32_t gv, tag;
        do {
          asm volatile("{\n.reg .b64 t;\nld.relaxed.gpu.global.b64 t, [%2];\nmov.b64 {%0, %1}, t;\n}" : "=r"(gv), "=r"(tag) : "l"(&g_gate[bi * 128 + tx]) : "memory");
        } while (!__all_sync(0xffffffffu, tag == ep));
        const float omg = fmaxf(bf_round(1.0f - __uint_as_float(gv)), 9.3132257e-10f);
        sts32(sb + SM_G + tx * 4, __float_as_uint(__fdividef(__uint_as_float(gv), omg)));
        sts32(sb + SM_G + 512 + (w * 32 + ((lane >> 2) & 1) * 16 + (lane >> 3) * 4 + (lane & 3)) * 4, __float_as_uint(omg));
        __syncwarp();
        mbar_arrive_if(BAR(B_G), lane == 0);
      } else {
        nb_sync(4, 128);
        const float qs = 0.25f * 1.4426950408889634f;
        const uint32_t qa = sb + SM_Q + (2 * w + ((lane >> 3) & 1)) * 1024 + (lane >> 4) * 128 + (lane & 7) * 16;
#pragma unroll
        for (int c = 0; c < 16; c += 2) {
          const float* f = d + 4 * c;
          stsm4(qa + (c >> 3) * 8192 + (c & 7) * 128, pack2(f[0] * qs, f[1] * qs), pack2(f[2] * qs, f[3] * qs), pack2(f[4] * qs, f[5] * qs), pack2(f[6] * qs, f[7] * qs));
        }
#pragma unroll
        for (int z = 0; z < 3; z++) {
          const uint32_t one = 4 * z < 8 - 4 * bi ? 0u : 0x3F803F80u;
          asm volatile("st.shared.v4.b32 [%0], {%1, %1, %1, %1};" :: "r"(sb + SM_V + w * 4608 + 3072 + z * 512 + lane * 16), "r"(one) : "memory");
        }
        fence_async_smem();
        __syncwarp();
        mbar_arrive_if(BAR(B_Q), lane == 0);
        if (w == 0) TR(37);
      }
    }
    mbar_spin(BAR(B_G), 0);
    const float gr0 = lds32f(sb + SM_G + (wg * 64 + w * 16 + g) * 4), gr1 = lds32f(sb + SM_G + (wg * 64 + w * 16 + g + 8) * 4);
    const int D = 16 * w + g - 2 * t;
    const float fzero = __int_as_float(zero);
    float SA[40], SB[40], o[12], oc[10];
    uint32_t PA[20], PB[20], fail = 0;
    const uint32_t kb = ((sb + SM_K + wg * 256) >> 4) + (96u << 16), vb = ((sb + SM_V + wg * 256) >> 4) + (8u << 16);
    uint32_t qd = ((sb + SM_Q + wg * 8192) >> 4) + (64u << 16);
    unsigned char* op = g_o + (size_t)bi * 131072 + bj * 4096 + (wg * 64 + (w >> 1) * 32 + (g >> 1) * 8 + (w & 1) * 4 + (g & 1)) * 16 + t * 4 - 32768;
    auto QK = [&](float (&S)[40], int sg) { wgmma_sz_n80<1, 1>(S, mkd(qd, 8), mkd(kb + sg * 192, 8)); };
    auto PV = [&](const uint32_t (&P)[20], int sg, bool first) {
#pragma unroll
      for (int z = 0; z < 5; z++) {
        const int kk = z < 3 ? z + 1 : (z == 3 ? 0 : 4);
        const uint64_t db = mkd(vb + sg * 288 + kk * 16, 96);
        if (z == 0 && first) wgmma_rz_n24<0>(o, P[kk * 4], P[kk * 4 + 1], P[kk * 4 + 2], P[kk * 4 + 3], db);
        else wgmma_rs_n24<0>(o, P[kk * 4], P[kk * 4 + 1], P[kk * 4 + 2], P[kk * 4 + 3], db, 1);
      }
    };
    uint32_t me[4];
#pragma unroll
    for (int k = 0; k < 4; k++) me[k] = __shfl_sync(0xffffffffu, (16 * k + 1 <= D) ? 0xFFFFFFFFu : (16 * k <= D) ? 0x0000FFFFu : 0u, lane);
    auto umask = [&](int k) { return k < 2 * w ? 0xFFFFFFFFu : 0u; };
    auto merge = [&](float (&S)[40], int Dl, int sg) {
#pragma unroll
      for (int i = 0; i < 8; i++) {
        const int k = sg + 4 * (i >> 2) - ((i >> 1) & 1);
        if (k & 1) {
          uint32_t y;
          asm("lop3.b32 %0, %1, %2, %3, 0xE4;" : "=r"(y) : "r"(__float_as_uint(S[32 + i])), "r"(__float_as_uint(S[i])), "r"(umask(k)));
          S[i] = __uint_as_float(y);
        } else {
          S[i] = (8 * k + (i & 1) <= Dl) ? S[32 + i] : S[i];
        }
      }
    };
    auto exps = [&](float (&S)[40], int z0, int z1) {
#pragma unroll
      for (int z = z0; z < z1; z++) { const int i = z < 12 ? 8 + z : (z < 20 ? z - 12 : z); S[i] = ex2(S[i]); }
    };
    auto packs = [&](float (&S)[40], uint32_t (&P)[20], int sg, int z0, int z1) {
#pragma unroll
      for (int z = z0; z < z1; z += 2) {
        const int i = z < 12 ? 8 + z : (z < 20 ? z - 12 : z);
        P[i / 2] = pack2(S[i], S[i + 1]);
        if (i < 8) {
          const int k = sg + 4 * (i >> 2) - ((i >> 1) & 1);
          const uint32_t M = (k & 1) ? umask(k) : me[(k >> 1) & 3];
          P[16 + i / 2] = P[i / 2] & M; P[i / 2] &= ~M;
        }
      }
    };
    auto copy_o = [&]() {
#pragma unroll
      for (int i = 0; i < 8; i++) asm volatile("mul.f32 %0, %1, %2;" : "=f"(oc[i]) : "f"(o[i]), "f"((i & 2) ? gr1 : gr0));
      asm volatile("add.f32 %0, %1, %2;" : "=f"(oc[8]) : "f"(o[8]), "f"(fzero));
      asm volatile("add.f32 %0, %1, %2;" : "=f"(oc[9]) : "f"(o[10]), "f"(fzero));
    };
    auto store_o = [&](int s) {
      const bool safe = oc[8] > 5.4210109e-20f && oc[8] < 1.8446744e19f && oc[9] > 5.4210109e-20f && oc[9] < 1.8446744e19f;
      const bool ok = __all_sync(0xffffffffu, safe);
      float r0, r1;
      asm volatile("rcp.approx.ftz.f32 %0, %1;" : "=f"(r0) : "f"(oc[8])); asm volatile("rcp.approx.ftz.f32 %0, %1;" : "=f"(r1) : "f"(oc[9]));
      const uint32_t a = pack2(oc[0] * r0, oc[1] * r0), bb = pack2(oc[2] * r1, oc[3] * r1), c = pack2(oc[4] * r0, oc[5] * r0), d = pack2(oc[6] * r1, oc[7] * r1);
      asm volatile("{\n.reg .pred p;\nsetp.ne.b32 p, %5, 0;\n@p st.global.b32 [%0], %1;\n@p st.global.b32 [%0+32], %2;\n@p st.global.b32 [%0+2048], %3;\n@p st.global.b32 [%0+2080], %4;\n}"
                   :: "l"(op), "r"(a), "r"(bb), "r"(c), "r"(d), "r"((int)(ok && s >= 0)) : "memory");
      fail |= (ok || s < 0) ? 0u : (1u << (s & 3));
      __syncwarp();
      mbar_arrive_if(BAR(B_SO + s), lane == 0 && ok && s >= 0 && s < 3);
      op += 32768;
    };
#pragma unroll
    for (int i = 0; i < 20; i++) asm volatile("" : "=r"(PB[i]));
#pragma unroll
    for (int i = 0; i < 12; i++) asm volatile("" : "=f"(o[i]));
    mbar_spin(BAR(B_Q), 0);
    mbar_spin(BAR(B_KF + 3), 0);
    if (warp == 0) TR(4);
    wg_fence(); QK(SA, 0); wg_commit();
    mbar_spin(BAR(B_KF), 0);
    mbar_spin(BAR(B_GO), 0);
    if (warp == 0) TR(58);
#pragma unroll 1
    for (int s = 0; s < 4; s++) {
      int Dl = D; asm volatile("" : "+r"(Dl));
      auto step = [&](float (&Sc)[40], float (&Sn)[40], uint32_t (&Pc)[20], uint32_t (&Pp)[20], int sig) {
        if (sig == 0) { wg_wait<0>(); fence_regs(Sc); mbar_arrive_if(BAR(B_KE + 3), lane == 0); }
        fence_regs(Pp); fence_regs(o);
        if (sig == 3) qd += s < 3 ? 128 : 0;
        wg_fence();
        QK(Sn, (sig + 1) & 3);
        PV(Pp, (sig - 1) & 3, sig == 1);
        wg_commit();
        SCHED_BR();
        const uint32_t nb = BAR(B_KF + ((sig + 1) & 3)), np = (s + (sig >= 2)) & 1;
        const bool ready = mbar_test(nb, np);
        merge(Sc, Dl, sig);
        if (sig == 1) store_o(s - 1);
        exps(Sc, 0, 32); packs(Sc, Pc, sig, 0, 32);
        if (__builtin_expect(!ready, 0)) { mbar_spin(nb, np); SCHED_BAR(100 + sig * 8 + s, Pc, 20); }
        if (sig < 3) {
          wg_wait<0>(); fence_regs(Sn); fence_regs(o); fence_regs(Pp);
          mbar_arrive_if(BAR(B_KE + sig), lane == 0);
        }
        if (sig == 0) copy_o();
      };
      step(SA, SB, PA, PB, 0);
      step(SB, SA, PB, PA, 1);
      step(SA, SB, PA, PB, 2);
      step(SB, SA, PB, PA, 3);
      if (w == 0) TR(5 + wg * 4 + s);
    }
    wg_fence(); PV(PB, 3, false); wg_commit(); wg_wait<0>(); fence_regs(o);
    copy_o(); store_o(3);
    if (__builtin_expect(fail != 0, 0)) {
      attention_exact(scr, sb, fail, bi, bj, wg, w, lane);
    }
    __syncwarp();
    if (w == 0) TR(13 + wg);
    mbar_arrive_if(BAR(B_SO + 3), lane == 0);
    TR_END();
  }
#undef BAR
}

typedef CUresult (*EncodeFn)(CUtensorMap*, CUtensorMapDataType, cuuint32_t, void*, const cuuint64_t*, const cuuint64_t*, const cuuint32_t*,
                             const cuuint32_t*, CUtensorMapInterleave, CUtensorMapSwizzle, CUtensorMapL2promotion, CUtensorMapFloatOOBfill);

CUtensorMap make_map(EncodeFn enc, const void* ptr, int rank, const cuuint64_t* dims, const cuuint64_t* strides, const cuuint32_t* box, int kind = 0) {
  const bool raw = kind == 1;
  CUtensorMap tm;
  const cuuint32_t es[5] = {1, 1, 1, 1, 1};
  enc(&tm, raw ? CU_TENSOR_MAP_DATA_TYPE_UINT64 : CU_TENSOR_MAP_DATA_TYPE_BFLOAT16, rank, const_cast<void*>(ptr), dims, strides, box, es, CU_TENSOR_MAP_INTERLEAVE_NONE,
      raw ? CU_TENSOR_MAP_SWIZZLE_NONE : kind == 2 ? CU_TENSOR_MAP_SWIZZLE_64B : CU_TENSOR_MAP_SWIZZLE_128B, CU_TENSOR_MAP_L2_PROMOTION_L2_128B, CU_TENSOR_MAP_FLOAT_OOB_FILL_NONE);
  return tm;
}

}

extern "C" void kernel_launch(void* const* d_in, const int* in_sizes, int n_in, void* d_out, int out_size) {
  (void)in_sizes; (void)n_in; (void)out_size;
  const void *x = d_in[0], *wqkv = d_in[1], *wo = d_in[2], *w1 = d_in[4], *w2 = d_in[5], *gate_w = d_in[6];
  void* fn = nullptr;
  cudaDriverEntryPointQueryResult qr;
  cudaGetDriverEntryPoint("cuTensorMapEncodeTiled", &fn, cudaEnableDefault, &qr);
  EncodeFn enc = (EncodeFn)fn;
  const cuuint64_t dx[2] = {512, 2048}, sx[1] = {1024};            const cuuint32_t bx[2] = {64, 128};
  const cuuint64_t dout[5] = {512, 2, 4, 4, 64}, so[4] = {1024, 8192, 2048, 32768}; const cuuint32_t bo[5] = {64, 2, 4, 4, 1};
  const cuuint64_t dq[2] = {1536, 512}, sq[1] = {3072};            const cuuint32_t bq[2] = {64, 64};
  const cuuint64_t d1[2] = {1376, 512}, s1[1] = {2752};            const cuuint32_t b1[2] = {64, 64};
  const cuuint64_t d2[2] = {512, 1376}, s2[1] = {1024};            const cuuint32_t b2[2] = {64, 64};
  const cuuint64_t dw[4] = {512, 32, 4, 4}, sw[3] = {1024, 32768, 131072}; const cuuint32_t bw[4] = {64, 16, 2, 2};
  const CUtensorMap tm_x = make_map(enc, x, 2, dx, sx, bx), tm_wqkv = make_map(enc, wqkv, 2, dq, sq, bq), tm_w1 = make_map(enc, w1, 2, d1, s1, b1),
                    tm_w2 = make_map(enc, w2, 2, d2, s2, b2), tm_wo = make_map(enc, wo, 4, dw, sw, bw), tm_out = make_map(enc, d_out, 5, dout, so, bo);
  void* scr = nullptr;
  cudaGetSymbolAddress(&scr, g_scratch);
  const cuuint64_t dp[3] = {448, 512, 2}, sp[2] = {3072, 128};     const cuuint32_t bp[3] = {32, 128, 2};
  const cuuint64_t dk[2] = {1024, 512}, sk[1] = {8192};            const cuuint32_t bk[2] = {192, 2};
  const CUtensorMap tm_kv = make_map(enc, (char*)scr + G_KV, 2, dk, sk, bk, 1), tm_wq = make_map(enc, wqkv, 3, dp, sp, bp, 2);
  cudaFuncSetAttribute(fused_kernel, cudaFuncAttributeMaxDynamicSharedMemorySize, SM_TOTAL);
  fused_kernel<<<128, 512, SM_TOTAL>>>((unsigned char*)scr, (const unsigned char*)gate_w, (const unsigned char*)x, (const unsigned char*)wqkv, (unsigned char*)d_out, 0, (const unsigned char*)w1,
                                       (const unsigned char*)w2, (const unsigned char*)wo, tm_x, tm_wqkv, tm_wq, tm_w1, tm_w2, tm_wo, tm_out, tm_kv);
}
```
